```python
import torch

def _softmax(x, axis=-1):
    return torch.softmax(x, dim=axis)
def _gelu(x):
    return torch.nn.functional.gelu(x, approximate="tanh")
def _silu(x):
    return torch.nn.functional.silu(x)
def _sigmoid(x):
    return torch.sigmoid(x)
def _layernorm(x, axis=-1, eps=1e-5):
    m = x.mean(dim=axis, keepdim=True)
    v = x.var(dim=axis, keepdim=True, unbiased=False)
    return (x - m) / torch.sqrt(v + eps)
def _scatter_add(tgt, idx, src, axis=0):
    return tgt.clone().index_add_(axis, idx, src)
def _segment_sum(src, seg, n):
    out = torch.zeros((n,) + src.shape[1:], dtype=src.dtype)
    return out.index_add_(0, seg, src)
def _pad(x, pw):
    flat = tuple(v for pair in reversed(pw) for v in pair)
    return torch.nn.functional.pad(x, flat)

kernel_name = 'concat_heads__gqa_block_cached__mha_block_cached__near_ridge'

def setup_inputs():

    _w = (lambda a: (lambda t: t.to(torch.bfloat16) if t.is_floating_point() else t)(torch.as_tensor(a)))
    def _A_setup():
        B, Sq, D = 16, 96, 640
        Hq, Hkv, Sk, Dh = 32, 32, 512, 128
        assert Hq % Hkv == 0, (Hq, Hkv)
        return {
            "x": _w((lambda *s: torch.randn(*s, dtype=torch.bfloat16) * 0.8)(B, Sq, D)),
            "k_cache": _w((lambda *s: torch.randn(*s, dtype=torch.bfloat16) * 0.8)(B, Hkv, Sk, Dh)),
            "v_cache": _w((lambda *s: torch.randn(*s, dtype=torch.bfloat16) * 0.05)(B, Hkv, Sk, Dh)),
            "wq": _w((lambda *s: torch.randn(*s, dtype=torch.bfloat16) * 0.8)(D, Hq * Dh) * (D ** -0.5)),
            "wo": _w((lambda *s: torch.randn(*s, dtype=torch.bfloat16) * 0.05)(Hq * Dh, D) * ((Hq * Dh) ** -0.5)),
        }
    _A_in = _A_setup()

    def _B_setup():
        B, Sq, D = 16, 96, 640
        H, Sk, Dh = 32, 512, 128
        return {
            "x": _w((lambda *s: torch.randn(*s, dtype=torch.bfloat16) * 0.8)(B, Sq, D)),
            "k_cache": _w((lambda *s: torch.randn(*s, dtype=torch.bfloat16) * 0.8)(B, H, Sk, Dh)),
            "v_cache": _w((lambda *s: torch.randn(*s, dtype=torch.bfloat16) * 0.05)(B, H, Sk, Dh)),
            "wq": _w((lambda *s: torch.randn(*s, dtype=torch.bfloat16) * 0.8)(D, H * Dh) * (D ** -0.5)),
            "wo": _w((lambda *s: torch.randn(*s, dtype=torch.bfloat16) * 0.05)(H * Dh, D) * ((H * Dh) ** -0.5)),
        }
    _B_in = _B_setup()

    return {
        "A_x": _A_in["x"],
        "A_k_cache": _A_in["k_cache"],
        "A_v_cache": _A_in["v_cache"],
        "A_wq": _A_in["wq"],
        "A_wo": _A_in["wo"],
        "B_x": _B_in["x"],
        "B_k_cache": _B_in["k_cache"],
        "B_v_cache": _B_in["v_cache"],
        "B_wq": _B_in["wq"],
        "B_wo": _B_in["wo"],
    }

def reference(A_x, A_k_cache, A_v_cache, A_wq, A_wo, B_x, B_k_cache, B_v_cache, B_wq, B_wo):
    def _A_ref(x, k_cache, v_cache, wq, wo):
        B, Sq, D = x.shape
        Hq, Dh = 32, 128
        Hkv = k_cache.shape[1]
        rep = Hq // Hkv
        q = (lambda x, *d: x.permute(*d))((x @ wq).reshape(B, Sq, Hq, Dh), 0, 2, 1, 3)
        k = (lambda x, n, axis: torch.repeat_interleave(x, n, dim=axis))(k_cache, rep, axis=1)
        v = (lambda x, n, axis: torch.repeat_interleave(x, n, dim=axis))(v_cache, rep, axis=1)
        scores = torch.einsum("bhqd,bhkd->bhqk", q, k) * (Dh ** -0.5)
        p = _softmax(scores, axis=-1)
        o = torch.einsum("bhqk,bhkd->bhqd", p, v)
        return (lambda x, *d: x.permute(*d))(o, 0, 2, 1, 3).reshape(B, Sq, Hq * Dh) @ wo

    def _B_ref(x, k_cache, v_cache, wq, wo):
        B, Sq, D = x.shape
        H, Dh = 32, 128
        q = (lambda x, *d: x.permute(*d))((x @ wq).reshape(B, Sq, H, Dh), 0, 2, 1, 3)
        scores = torch.einsum("bhqd,bhkd->bhqk", q, k_cache) * (Dh ** -0.5)
        p = _softmax(scores, axis=-1)
        o = torch.einsum("bhqk,bhkd->bhqd", p, v_cache)
        return (lambda x, *d: x.permute(*d))(o, 0, 2, 1, 3).reshape(B, Sq, H * Dh) @ wo

    a = _A_ref(A_x, A_k_cache, A_v_cache, A_wq, A_wo)
    b = _B_ref(B_x, B_k_cache, B_v_cache, B_wq, B_wo)
    return torch.concatenate([a, b], axis=-1)
```

```cpp
#include <cuda_runtime.h>
#include <cuda_bf16.h>
#include <cuda.h>
#include <stdint.h>

namespace {

constexpr int NB = 16, SQ = 96, DM = 640, NH = 32, SK = 512, DH = 128;
constexpr int ROWS = NB * SQ;
constexpr int HD = NH * DH;
constexpr int NROUND = 8;

constexpr int KVS = 5;
constexpr int WS = 3;
constexpr int XS = 3;
constexpr int O_SINGLE = 2;
constexpr int KV_TAU = 700;
constexpr int BOOST = 96;
constexpr int STAGT = 80;
constexpr int VREL_Q = 3;
constexpr int PDEPTH = 1;

constexpr int TILE = 16384;
constexpr int KV_SLOTS = KVS;
constexpr int W_SLOTS = WS;
constexpr int X_SLOTS = XS;
constexpr int Q_HALF = SQ * 128;
constexpr int Q_BYTES = 2 * Q_HALF;
constexpr int OFF_Q = 0;
constexpr int OFF_P = OFF_Q + Q_BYTES;
constexpr int OFF_KV = OFF_P + Q_BYTES;
constexpr int OFF_W = OFF_KV + KV_SLOTS * TILE;
constexpr int OFF_X = OFF_W + W_SLOTS * TILE;
constexpr int OFF_MC = OFF_X + X_SLOTS * TILE;
constexpr int OFF_FAC = OFF_MC + 384;
constexpr int OFF_LP = OFF_FAC + 384;
constexpr int OFF_BAR = OFF_LP + 1536;
constexpr int SMEM_BYTES = OFF_BAR + 256;
static_assert(KV_SLOTS >= 4 && W_SLOTS >= 3 && X_SLOTS >= 3, "tail slots");
__host__ __device__ constexpr int tail_slot(int i) { return (NROUND * 16 + i) % KV_SLOTS; }
static_assert(W_SLOTS + KV_SLOTS <= 10 && X_SLOTS + 4 <= 10, "prologue");
static_assert(SMEM_BYTES <= 232448, "smem");
constexpr int O_BLOCKS = 8 - O_SINGLE;
__host__ __device__ constexpr int o_block(int r, int j) { return j < O_SINGLE ? j : 2 * j - O_SINGLE + (r & 1); }
constexpr float T_LIMIT = 10.f;

struct Maps {
  CUtensorMap k[2], v[2], x[2], wq[2], wo[2], oload, ostore;
  const uint8_t* pwq[2];
  const uint8_t* pwo[2];
  uint8_t* pout;
};

__device__ __align__(1024) __nv_bfloat16 g_O[2 * ROWS * O_BLOCKS * DH];
__device__ unsigned g_flags[2 * NB * NH];
__device__ unsigned g_used[24 * NH];
__device__ unsigned g_prog;
__device__ unsigned g_epoch;
__device__ unsigned g_done;

__device__ __forceinline__ uint32_t smem_u32(const void* p) { return (uint32_t)__cvta_generic_to_shared(p); }
__device__ __forceinline__ void mbar_init(uint32_t bar, int cnt) {
  asm volatile("mbarrier.init.shared::cta.b64 [%0], %1;" ::"r"(bar), "r"(cnt) : "memory");
}
__device__ __forceinline__ void mbar_expect_tx(uint32_t bar, uint32_t bytes) {
  asm volatile("mbarrier.arrive.expect_tx.shared::cta.b64 _, [%0], %1;" ::"r"(bar), "r"(bytes) : "memory");
}
__device__ __forceinline__ void mbar_arrive(uint32_t bar) {
  asm volatile("mbarrier.arrive.shared::cta.b64 _, [%0];" ::"r"(bar) : "memory");
}
__device__ __forceinline__ void mbar_wait(uint32_t bar, uint32_t parity) {
  asm volatile(
      "{\n.reg .pred p;\n.reg .u32 n;\n"
      "mbarrier.try_wait.parity.shared::cta.b64 p, [%0], %1;\n"
      "@p bra WAIT_DONE;\n"
      "mov.u32 n, 0;\n"
      "WAIT_LOOP:\n"
      "mbarrier.try_wait.parity.shared::cta.b64 p, [%0], %1;\n"
      "@p bra WAIT_DONE;\n"
      "add.u32 n, n, 1;\n"
      "setp.lt.u32 p, n, 2097152;\n"
      "@p bra WAIT_LOOP;\n"
      "trap;\n"
      "WAIT_DONE:\n}\n" ::"r"(bar), "r"(parity) : "memory");
}
__device__ __forceinline__ void mbar_wait2(uint32_t b0, uint32_t p0, uint32_t b1, uint32_t p1) {
  asm volatile(
      "{\n.reg .pred p, q;\n.reg .u32 n;\n"
      "mbarrier.try_wait.parity.shared::cta.b64 p, [%0], %1;\n"
      "mbarrier.try_wait.parity.shared::cta.b64 q, [%2], %3;\n"
      "and.pred p, p, q;\n"
      "@p bra WAIT_DONE;\n"
      "mov.u32 n, 0;\n"
      "WAIT_LOOP:\n"
      "mbarrier.try_wait.parity.shared::cta.b64 p, [%0], %1;\n"
      "mbarrier.try_wait.parity.shared::cta.b64 q, [%2], %3;\n"
      "and.pred p, p, q;\n"
      "@p bra WAIT_DONE;\n"
      "add.u32 n, n, 1;\n"
      "setp.lt.u32 p, n, 2097152;\n"
      "@p bra WAIT_LOOP;\n"
      "trap;\n"
      "WAIT_DONE:\n}\n" ::"r"(b0), "r"(p0), "r"(b1), "r"(p1) : "memory");
}
__device__ __forceinline__ uint32_t mbar_test(uint32_t bar, uint32_t parity) {
  uint32_t ok;
  asm volatile("{\n.reg .pred p;\nmbarrier.test_wait.parity.shared::cta.b64 p, [%1], %2;\nselp.u32 %0, 1, 0, p;\n}\n"
               : "=r"(ok) : "r"(bar), "r"(parity) : "memory");
  return ok;
}
__device__ __forceinline__ uint32_t mbar_test2(uint32_t b0, uint32_t p0, uint32_t b1, uint32_t p1) {
  uint32_t ok;
  asm volatile("{\n.reg .pred p, q;\nmbarrier.test_wait.parity.shared::cta.b64 p, [%1], %2;\n"
               "mbarrier.test_wait.parity.shared::cta.b64 q, [%3], %4;\nand.pred p, p, q;\nselp.u32 %0, 1, 0, p;\n}\n"
               : "=r"(ok) : "r"(b0), "r"(p0), "r"(b1), "r"(p1) : "memory");
  return ok;
}
__device__ __forceinline__ void arrive_if(uint32_t bar, uint32_t pred) {
  asm volatile("{\n.reg .pred p;\nsetp.ne.u32 p, %1, 0;\n@p mbarrier.arrive.shared::cta.b64 _, [%0];\n}\n" ::"r"(bar), "r"(pred) : "memory");
}
__device__ __forceinline__ void arrive_cluster_if(uint32_t bar, uint32_t pred) {
  asm volatile("{\n.reg .pred p;\nsetp.ne.u32 p, %1, 0;\n@p mbarrier.arrive.shared::cluster.b64 _, [%0];\n}\n" ::"r"(bar), "r"(pred) : "memory");
}
__device__ __forceinline__ bool elect_one() {
  uint32_t p;
  asm volatile("{\n.reg .pred P;\nelect.sync _|P, 0xffffffff;\nselp.u32 %0, 1, 0, P;\n}\n" : "=r"(p));
  return p;
}
__device__ __forceinline__ void tma2d(uint32_t dst, const CUtensorMap* m, int c0, int c1, uint32_t bar) {
  asm volatile("cp.async.bulk.tensor.2d.shared::cluster.global.mbarrier::complete_tx::bytes [%0], [%1, {%3, %4}], [%2];"
               ::"r"(dst), "l"(m), "r"(bar), "r"(c0), "r"(c1) : "memory");
}
__device__ __forceinline__ void tma3d_hint(uint32_t dst, const CUtensorMap* m, int c0, int c1, int c2, uint32_t bar, uint64_t pol) {
  asm volatile("cp.async.bulk.tensor.3d.shared::cluster.global.mbarrier::complete_tx::bytes.L2::cache_hint [%0], [%1, {%3, %4, %5}], [%2], %6;"
               ::"r"(dst), "l"(m), "r"(bar), "r"(c0), "r"(c1), "r"(c2), "l"(pol) : "memory");
}
__device__ __forceinline__ void tma2d_mc(uint32_t dst, const CUtensorMap* m, int c0, int c1, uint32_t bar, uint16_t mask) {
  asm volatile("cp.async.bulk.tensor.2d.shared::cluster.global.mbarrier::complete_tx::bytes.multicast::cluster [%0], [%1, {%3, %4}], [%2], %5;"
               ::"r"(dst), "l"(m), "r"(bar), "r"(c0), "r"(c1), "h"(mask) : "memory");
}
__device__ __forceinline__ void tma2d_store(const CUtensorMap* m, int c0, int c1, uint32_t src) {
  asm volatile("cp.async.bulk.tensor.2d.global.shared::cta.bulk_group [%0, {%2, %3}], [%1];"
               ::"l"(m), "r"(src), "r"(c0), "r"(c1) : "memory");
}
__device__ __forceinline__ uint32_t now_ns() {
  uint32_t t;
  asm volatile("mov.u32 %0, %%globaltimer_lo;" : "=r"(t));
  return t;
}
__device__ __forceinline__ void prefetch_l2(const void* p, uint32_t bytes) {
  asm volatile("cp.async.bulk.prefetch.L2.global [%0], %1;" ::"l"(p), "r"(bytes) : "memory");
}
__device__ __forceinline__ void wg_fence() { asm volatile("wgmma.fence.sync.aligned;" ::: "memory"); }
__device__ __forceinline__ void wg_commit() { asm volatile("wgmma.commit_group.sync.aligned;" ::: "memory"); }
template <int N> __device__ __forceinline__ void wg_wait() { asm volatile("wgmma.wait_group.sync.aligned %0;" ::"n"(N) : "memory"); }
template <int N> __device__ __forceinline__ void pin(float (&d)[N]) {
#pragma unroll
  for (int i = 0; i < N; i++) asm volatile("" : "+f"(d[i])::"memory");
}
__device__ __forceinline__ void sts32(uint32_t a, float v) { asm volatile("st.shared.f32 [%0], %1;" ::"r"(a), "f"(v) : "memory"); }
__device__ __forceinline__ void bar_sync_wg() { asm volatile("bar.sync 1, 128;" ::: "memory"); }
__device__ __forceinline__ bool bar_or_wg(bool f) {
  uint32_t r;
  asm volatile("{\n.reg .pred p, q;\nsetp.ne.u32 p, %1, 0;\nbar.red.or.pred q, 1, 128, p;\nselp.u32 %0, 1, 0, q;\n}\n"
               : "=r"(r) : "r"((uint32_t)f) : "memory");
  return r;
}
__device__ __forceinline__ uint32_t pack_bf16(float lo, float hi) {
  uint32_t r;
  asm("cvt.rn.bf16x2.f32 %0, %1, %2;" : "=r"(r) : "f"(hi), "f"(lo));
  return r;
}
__device__ __forceinline__ float ex2(float x) {
  float y;
  asm("ex2.approx.ftz.f32 %0, %1;" : "=f"(y) : "f"(x));
  return y;
}
__device__ __forceinline__ void stsm4(uint32_t addr, uint32_t a, uint32_t b, uint32_t c, uint32_t d) {
  asm volatile("stmatrix.sync.aligned.m8n8.x4.shared.b16 [%0], {%1, %2, %3, %4};" ::"r"(addr), "r"(a), "r"(b), "r"(c), "r"(d) : "memory");
}
__device__ __forceinline__ void stsm4_t(uint32_t addr, uint32_t a, uint32_t b, uint32_t c, uint32_t d) {
  asm volatile("stmatrix.sync.aligned.m8n8.x4.trans.shared.b16 [%0], {%1, %2, %3, %4};" ::"r"(addr), "r"(a), "r"(b), "r"(c), "r"(d));
}
__device__ __forceinline__ void fence_async_smem() { asm volatile("fence.proxy.async.shared::cta;" ::: "memory"); }

__device__ __forceinline__ void mma_t96(float (&d)[48], uint32_t alo, uint32_t blo) {
  asm volatile("{\n.reg .b64 da, db;\nmov.b64 da, {%48, %50};\nmov.b64 db, {%49, %50};\n"
    "wgmma.mma_async.sync.aligned.m64n96k16.f32.bf16.bf16 {%0, %1, %2, %3, %4, %5, %6, %7, %8, %9, %10, %11, %12, %13, %14, %15, %16, %17, %18, %19, %20, %21, %22, %23, %24, %25, %26, %27, %28, %29, %30, %31, %32, %33, %34, %35, %36, %37, %38, %39, %40, %41, %42, %43, %44, %45, %46, %47}, da, db, 1, 1, 1, 1, 0;\n}\n"
    : "+f"(d[0]), "+f"(d[1]), "+f"(d[2]), "+f"(d[3]), "+f"(d[4]), "+f"(d[5]), "+f"(d[6]), "+f"(d[7]), "+f"(d[8]), "+f"(d[9]), "+f"(d[10]), "+f"(d[11]), "+f"(d[12]), "+f"(d[13]), "+f"(d[14]), "+f"(d[15]), "+f"(d[16]), "+f"(d[17]), "+f"(d[18]), "+f"(d[19]), "+f"(d[20]), "+f"(d[21]), "+f"(d[22]), "+f"(d[23]), "+f"(d[24]), "+f"(d[25]), "+f"(d[26]), "+f"(d[27]), "+f"(d[28]), "+f"(d[29]), "+f"(d[30]), "+f"(d[31]), "+f"(d[32]), "+f"(d[33]), "+f"(d[34]), "+f"(d[35]), "+f"(d[36]), "+f"(d[37]), "+f"(d[38]), "+f"(d[39]), "+f"(d[40]), "+f"(d[41]), "+f"(d[42]), "+f"(d[43]), "+f"(d[44]), "+f"(d[45]), "+f"(d[46]), "+f"(d[47])
    : "r"(alo), "r"(blo), "r"(0x40000040u));
}
__device__ __forceinline__ void mma_t96p(float (&d)[48], uint32_t alo, uint32_t blo, uint32_t acc) {
  asm volatile("{\n.reg .b64 da, db;\n.reg .pred p;\nsetp.ne.u32 p, %51, 0;\nmov.b64 da, {%48, %50};\nmov.b64 db, {%49, %50};\n"
    "wgmma.mma_async.sync.aligned.m64n96k16.f32.bf16.bf16 {%0, %1, %2, %3, %4, %5, %6, %7, %8, %9, %10, %11, %12, %13, %14, %15, %16, %17, %18, %19, %20, %21, %22, %23, %24, %25, %26, %27, %28, %29, %30, %31, %32, %33, %34, %35, %36, %37, %38, %39, %40, %41, %42, %43, %44, %45, %46, %47}, da, db, p, 1, 1, 1, 0;\n}\n"
    : "+f"(d[0]), "+f"(d[1]), "+f"(d[2]), "+f"(d[3]), "+f"(d[4]), "+f"(d[5]), "+f"(d[6]), "+f"(d[7]), "+f"(d[8]), "+f"(d[9]), "+f"(d[10]), "+f"(d[11]), "+f"(d[12]), "+f"(d[13]), "+f"(d[14]), "+f"(d[15]), "+f"(d[16]), "+f"(d[17]), "+f"(d[18]), "+f"(d[19]), "+f"(d[20]), "+f"(d[21]), "+f"(d[22]), "+f"(d[23]), "+f"(d[24]), "+f"(d[25]), "+f"(d[26]), "+f"(d[27]), "+f"(d[28]), "+f"(d[29]), "+f"(d[30]), "+f"(d[31]), "+f"(d[32]), "+f"(d[33]), "+f"(d[34]), "+f"(d[35]), "+f"(d[36]), "+f"(d[37]), "+f"(d[38]), "+f"(d[39]), "+f"(d[40]), "+f"(d[41]), "+f"(d[42]), "+f"(d[43]), "+f"(d[44]), "+f"(d[45]), "+f"(d[46]), "+f"(d[47])
    : "r"(alo), "r"(blo), "r"(0x40000040u), "r"(acc));
}
__device__ __forceinline__ void mma_qk(float (&d)[48], uint32_t alo, uint32_t blo) {
  asm volatile("{\n.reg .b64 da, db;\nmov.b64 da, {%48, %50};\nmov.b64 db, {%49, %50};\n"
    "wgmma.mma_async.sync.aligned.m64n96k16.f32.bf16.bf16 {%0, %1, %2, %3, %4, %5, %6, %7, %8, %9, %10, %11, %12, %13, %14, %15, %16, %17, %18, %19, %20, %21, %22, %23, %24, %25, %26, %27, %28, %29, %30, %31, %32, %33, %34, %35, %36, %37, %38, %39, %40, %41, %42, %43, %44, %45, %46, %47}, da, db, 1, 1, 1, 0, 0;\n}\n"
    : "+f"(d[0]), "+f"(d[1]), "+f"(d[2]), "+f"(d[3]), "+f"(d[4]), "+f"(d[5]), "+f"(d[6]), "+f"(d[7]), "+f"(d[8]), "+f"(d[9]), "+f"(d[10]), "+f"(d[11]), "+f"(d[12]), "+f"(d[13]), "+f"(d[14]), "+f"(d[15]), "+f"(d[16]), "+f"(d[17]), "+f"(d[18]), "+f"(d[19]), "+f"(d[20]), "+f"(d[21]), "+f"(d[22]), "+f"(d[23]), "+f"(d[24]), "+f"(d[25]), "+f"(d[26]), "+f"(d[27]), "+f"(d[28]), "+f"(d[29]), "+f"(d[30]), "+f"(d[31]), "+f"(d[32]), "+f"(d[33]), "+f"(d[34]), "+f"(d[35]), "+f"(d[36]), "+f"(d[37]), "+f"(d[38]), "+f"(d[39]), "+f"(d[40]), "+f"(d[41]), "+f"(d[42]), "+f"(d[43]), "+f"(d[44]), "+f"(d[45]), "+f"(d[46]), "+f"(d[47])
    : "r"(alo), "r"(blo), "r"(0x40000040u));
}
__device__ __forceinline__ void mma_qk0(float (&d)[48], uint32_t alo, uint32_t blo) {
  asm volatile("{\n.reg .b64 da, db;\nmov.b64 da, {%48, %50};\nmov.b64 db, {%49, %50};\n"
    "wgmma.mma_async.sync.aligned.m64n96k16.f32.bf16.bf16 {%0, %1, %2, %3, %4, %5, %6, %7, %8, %9, %10, %11, %12, %13, %14, %15, %16, %17, %18, %19, %20, %21, %22, %23, %24, %25, %26, %27, %28, %29, %30, %31, %32, %33, %34, %35, %36, %37, %38, %39, %40, %41, %42, %43, %44, %45, %46, %47}, da, db, 0, 1, 1, 0, 0;\n}\n"
    : "=f"(d[0]), "=f"(d[1]), "=f"(d[2]), "=f"(d[3]), "=f"(d[4]), "=f"(d[5]), "=f"(d[6]), "=f"(d[7]), "=f"(d[8]), "=f"(d[9]), "=f"(d[10]), "=f"(d[11]), "=f"(d[12]), "=f"(d[13]), "=f"(d[14]), "=f"(d[15]), "=f"(d[16]), "=f"(d[17]), "=f"(d[18]), "=f"(d[19]), "=f"(d[20]), "=f"(d[21]), "=f"(d[22]), "=f"(d[23]), "=f"(d[24]), "=f"(d[25]), "=f"(d[26]), "=f"(d[27]), "=f"(d[28]), "=f"(d[29]), "=f"(d[30]), "=f"(d[31]), "=f"(d[32]), "=f"(d[33]), "=f"(d[34]), "=f"(d[35]), "=f"(d[36]), "=f"(d[37]), "=f"(d[38]), "=f"(d[39]), "=f"(d[40]), "=f"(d[41]), "=f"(d[42]), "=f"(d[43]), "=f"(d[44]), "=f"(d[45]), "=f"(d[46]), "=f"(d[47])
    : "r"(alo), "r"(blo), "r"(0x40000040u));
}
__device__ __forceinline__ void mma_op(float (&d)[64], uint32_t alo, uint32_t blo) {
  asm volatile("{\n.reg .b64 da, db;\nmov.b64 da, {%64, %66};\nmov.b64 db, {%65, %66};\n"
    "wgmma.mma_async.sync.aligned.m64n128k16.f32.bf16.bf16 {%0, %1, %2, %3, %4, %5, %6, %7, %8, %9, %10, %11, %12, %13, %14, %15, %16, %17, %18, %19, %20, %21, %22, %23, %24, %25, %26, %27, %28, %29, %30, %31, %32, %33, %34, %35, %36, %37, %38, %39, %40, %41, %42, %43, %44, %45, %46, %47, %48, %49, %50, %51, %52, %53, %54, %55, %56, %57, %58, %59, %60, %61, %62, %63}, da, db, 1, 1, 1, 0, 1;\n}\n"
    : "+f"(d[0]), "+f"(d[1]), "+f"(d[2]), "+f"(d[3]), "+f"(d[4]), "+f"(d[5]), "+f"(d[6]), "+f"(d[7]), "+f"(d[8]), "+f"(d[9]), "+f"(d[10]), "+f"(d[11]), "+f"(d[12]), "+f"(d[13]), "+f"(d[14]), "+f"(d[15]), "+f"(d[16]), "+f"(d[17]), "+f"(d[18]), "+f"(d[19]), "+f"(d[20]), "+f"(d[21]), "+f"(d[22]), "+f"(d[23]), "+f"(d[24]), "+f"(d[25]), "+f"(d[26]), "+f"(d[27]), "+f"(d[28]), "+f"(d[29]), "+f"(d[30]), "+f"(d[31]), "+f"(d[32]), "+f"(d[33]), "+f"(d[34]), "+f"(d[35]), "+f"(d[36]), "+f"(d[37]), "+f"(d[38]), "+f"(d[39]), "+f"(d[40]), "+f"(d[41]), "+f"(d[42]), "+f"(d[43]), "+f"(d[44]), "+f"(d[45]), "+f"(d[46]), "+f"(d[47]), "+f"(d[48]), "+f"(d[49]), "+f"(d[50]), "+f"(d[51]), "+f"(d[52]), "+f"(d[53]), "+f"(d[54]), "+f"(d[55]), "+f"(d[56]), "+f"(d[57]), "+f"(d[58]), "+f"(d[59]), "+f"(d[60]), "+f"(d[61]), "+f"(d[62]), "+f"(d[63])
    : "r"(alo), "r"(blo), "r"(0x40000040u));
}

constexpr uint32_t LBO1 = 1u << 16, LBO8K = 512u << 16, LBO1K = 64u << 16;

__global__ void __cluster_dims__(2, 1, 1) __launch_bounds__(384, 1)
fused_attn_kernel(const __grid_constant__ Maps maps) {
  extern __shared__ __align__(1024) uint8_t smem_raw[];
  const uint32_t sbase = smem_u32(smem_raw);
  const uint32_t bar_kv_full = sbase + OFF_BAR;
  const uint32_t bar_kv_empty = bar_kv_full + 8 * KV_SLOTS;
  const uint32_t bar_w_full = bar_kv_empty + 8 * KV_SLOTS;
  const uint32_t bar_w_empty = bar_w_full + 8 * W_SLOTS;
  const uint32_t bar_x_full = bar_w_empty + 8 * W_SLOTS;
  const uint32_t bar_x_empty = bar_x_full + 8 * X_SLOTS;
  const uint32_t bar_o_staged = bar_x_empty + 8 * X_SLOTS;
  const uint32_t bar_o_free = bar_o_staged + 8;
  const uint32_t bar_q_ready = bar_o_free + 8;
  const uint32_t bar_q_free = bar_q_ready + 8;
  const uint32_t bar_x0 = bar_q_free + 8;

  const int warp = __shfl_sync(0xffffffff, threadIdx.x >> 5, 0);
  const int lane = threadIdx.x & 31;
  if (warp == 11) {
    if (elect_one()) {
#pragma unroll
      for (int i = 0; i < KV_SLOTS; i++) { mbar_init(bar_kv_full + 8 * i, 1); mbar_init(bar_kv_empty + 8 * i, 4); }
#pragma unroll
      for (int i = 0; i < W_SLOTS; i++) { mbar_init(bar_w_full + 8 * i, 1); mbar_init(bar_w_empty + 8 * i, 8); }
#pragma unroll
      for (int i = 0; i < X_SLOTS; i++) { mbar_init(bar_x_full + 8 * i, 1); mbar_init(bar_x_empty + 8 * i, 4); }
      mbar_init(bar_o_staged, 4);
      mbar_init(bar_o_free, 1);
      mbar_init(bar_q_ready, 4);
      mbar_init(bar_q_free, 4);
#pragma unroll
      for (int i = 0; i < 4; i++) mbar_init(bar_x0 + 8 * i, 1);
      if (sbase & 1023) asm volatile("trap;");
      asm volatile("fence.mbarrier_init.release.cluster;" ::: "memory");
      fence_async_smem();
    }
    __syncwarp();
  }
  asm volatile("barrier.cluster.arrive.relaxed.aligned;" ::: "memory");
  const int rank = blockIdx.x & 1;
  const int cl = blockIdx.x >> 1;
  const int g7 = (cl - 36) % 7;
  const int grp = cl < 4 ? 9 : cl < 36 ? 2 * ((cl - 4) & 7) : 2 * (g7 + (g7 >= 4)) + 1;
  const int hj = cl < 4 ? cl : cl < 36 ? (cl - 4) >> 3 : (cl - 36) / 7;
  const int branch = grp >> 3;
  const int bp = grp & 7;
  const int bidx = bp * 2 + rank;
  const int c64 = (bp * 4 + hj) * 2 + rank;
  auto quad_of = [&](int r) { return (r + 3 * branch) & (NROUND - 1); };
  const bool odd = bp & 1;
  const bool share_o = odd ? hj >= 2 : hj == 3;
  const int tcol = odd ? (hj < 2 ? 3 + hj : hj == 2 ? rank : 2) : (hj < 3 ? hj : 3 + rank);
  const int trow = (bp >> 1) * 3 + ((!share_o && rank) ? 1 : odd ? 2 : 0);
  const bool store_tile = !(odd && hj == 3 && rank);

  if (warp == 11) {
    if (elect_one()) {
#pragma unroll
      for (int i = 0; i < 10; i++) {
        if (i < X_SLOTS + 4) {
          const uint32_t bar = i < X_SLOTS ? bar_x_full + 8 * i : bar_x0 + 8 * (i - X_SLOTS);
          mbar_expect_tx(bar, Q_HALF);
          tma2d(i < X_SLOTS ? sbase + OFF_X + i * TILE : sbase + OFF_Q + (i - X_SLOTS) * Q_HALF, &maps.x[branch], i * 64, bidx * SQ, bar);
        } else {
          asm volatile("cp.async.bulk.prefetch.tensor.2d.L2.global [%0, {%1, %2}];" ::"l"(&maps.x[branch]), "r"(i * 64), "r"(bidx * SQ) : "memory");
        }
      }
    }
    __syncwarp();
  } else if (warp == 8) {
    if (lane == 0)
      asm volatile("cp.async.bulk.prefetch.tensor.3d.L2.global [%0, {%1, %2, %3}];" ::"l"(&maps.k[branch]), "r"(0),
                   "r"((bidx * NH + 4 * quad_of(0) + hj) * SK + 4 * rank * 64), "r"(0) : "memory");
  } else if (warp == 10) {
    if (lane < 12) asm volatile("prefetch.tensormap [%0];" ::"l"(reinterpret_cast<const CUtensorMap*>(&maps) + lane) : "memory");
  }
  asm volatile("barrier.cluster.wait.aligned;" ::: "memory");
  if (warp == 9) {
    if (elect_one()) {
#pragma unroll
      for (int i = 0; i < 10; i++) {
        if (i < W_SLOTS + KV_SLOTS) {
          const uint32_t bar = i < W_SLOTS ? bar_w_full + 8 * i : bar_kv_full + 8 * (i - W_SLOTS);
          mbar_expect_tx(bar, TILE);
          tma2d_mc((i < W_SLOTS ? sbase + OFF_W + i * TILE : sbase + OFF_KV + (i - W_SLOTS) * TILE) + rank * 8192, &maps.wq[branch],
                   (4 * quad_of(0) + hj) * DH + rank * 64, i * 64, bar, (uint16_t)3);
        } else {
          asm volatile("cp.async.bulk.prefetch.tensor.2d.L2.global [%0, {%1, %2}];" ::"l"(&maps.wq[branch]), "r"((4 * quad_of(0) + hj) * DH + rank * 64), "r"(i * 64) : "memory");
        }
      }
    }
    __syncwarp();
  }

  if (warp >= 8) {
    asm volatile("setmaxnreg.dec.sync.aligned.u32 24;");
    if (warp == 8) {
      uint64_t pol;
      asm volatile("createpolicy.fractional.L2::evict_first.b64 %0, 1.0;" : "=l"(pol));
      const CUtensorMap* mk = &maps.k[branch];
      const CUtensorMap* mv = &maps.v[branch];
      int slot = 0; uint32_t ph = 0;
      uint32_t tlast = 0;
      const uint32_t tag = __shfl_sync(0xffffffff, *(volatile unsigned*)&g_epoch + 1, 0);
      uint32_t total = 0;
      int lead = 0;
      uint32_t h1 = 0, h2 = 0, h3 = 0;
#pragma unroll 1
      for (int c = 0; c < NROUND * 16; c++) {
        const int e = c & 15;
        const bool isk = (e == 0) || ((e & 1) && e < 15);
        const int m = isk ? (e + 1) >> 1 : (e - 1) >> 1;
        const uint32_t bar = bar_kv_full + 8 * slot;
        if (c >= 3 && lead >= -BOOST) {
          mbar_wait(h3 & ~1u, h3 & 1u);
          const int tau = lead > BOOST ? 5000 : KV_TAU;
          for (int n = 0; n < 1024 && !mbar_test(h2 & ~1u, h2 & 1u) && (int)(now_ns() - tlast) < tau; n++) __nanosleep(40);
        }
        mbar_wait(bar_kv_empty + 8 * slot, ph);
        if (elect_one()) {
          mbar_expect_tx(bar, TILE);
          tma3d_hint(sbase + OFF_KV + slot * TILE, isk ? mk : mv, 0, (bidx * NH + 4 * quad_of(c >> 4) + hj) * SK + (m ^ (4 * rank)) * 64, 0, bar, pol);
        }
        tlast = now_ns();
        if ((c & 3) == 1 && c > 4) lead = (c - 1) * 128 - (int)__shfl_sync(0xffffffff, total, 0) - 256 + (2 * hj - 3) * STAGT;
        if ((c & 3) == 3 && c < NROUND * 16 - 4 && lane == 0) total = atomicAdd(&g_prog, 4u);
        h3 = h2; h2 = h1; h1 = bar | (ph ^ 1);
        if (++slot == KV_SLOTS) { slot = 0; ph ^= 1; }
      }
      {
        const int blo = (trow * 128) / SQ, bhi = (trow * 128 + 127) / SQ;
#pragma unroll 1
        for (int i = 0; i < 4; i++) {
          const int go = 8 * (NROUND - 1) + 3 + (i & 1);
          mbar_wait(bar_kv_empty + 8 * slot, ph);
          if (i >= 2) {
            const unsigned* f = g_flags + (branch * NB + ((lane & 1) ? bhi : blo)) * NH + (go >> 1);
            uint32_t n = 0;
            while (true) {
              unsigned v;
              asm volatile("ld.acquire.gpu.global.u32 %0, [%1];" : "=r"(v) : "l"(f) : "memory");
              if (__all_sync(0xffffffff, v == tag)) break;
              if (++n > (1u << 22)) asm volatile("trap;");
            }
            asm volatile("fence.proxy.async.global;" ::: "memory");
          }
          if (elect_one()) {
            const uint32_t bar = bar_x0 + 8 * i, dst = sbase + OFF_KV + slot * TILE;
            const CUtensorMap* m = i >= 2 ? &maps.oload : &maps.wo[branch];
            const int c0 = i >= 2 ? o_block(go >> 3, (go >> 1) & 3) * DH + (go & 1) * 64 : tcol * 128;
            const int c1 = i >= 2 ? branch * ROWS + trow * 128 : (8 * quad_of(go >> 3) + (go & 7)) * 64;
            mbar_expect_tx(bar, TILE);
            tma2d(dst, m, c0, c1, bar);
            tma2d(dst + 8192, m, c0 + (i >= 2 ? 0 : 64), c1 + (i >= 2 ? 64 : 0), bar);
          }
          if (++slot == KV_SLOTS) { slot = 0; ph ^= 1; }
        }
      }
    } else if (warp == 9 || warp == 11) {
      const bool isw = (warp == 9);
      unsigned tag = 0;
      const int blo = (trow * 128) / SQ, bhi = (trow * 128 + 127) / SQ;
      const unsigned* myflag = g_flags + (branch * NB + ((lane & 1) ? bhi : blo)) * NH + ((lane >> 1) & 3);
      uint32_t seen = 0;
      const int nslots = isw ? W_SLOTS : X_SLOTS;
      const uint32_t bfull = isw ? bar_w_full : bar_x_full;
      const uint32_t bempty = isw ? bar_w_empty : bar_x_empty;
      const uint32_t ring = sbase + (isw ? OFF_W + rank * 8192 : OFF_X);
      int slot = 0; uint32_t ph = 0;
      int gq = isw ? W_SLOTS + KV_SLOTS : X_SLOTS + 4, go = 0;
      auto load_qp = [&]() {
        const int rr = gq / 10, kc = gq - rr * 10;
        mbar_wait(bempty + 8 * slot, ph);
        if (elect_one()) {
          const uint32_t bar = bfull + 8 * slot, dst = ring + slot * TILE;
          if (isw) {
            mbar_expect_tx(bar, TILE);
            tma2d_mc(dst, &maps.wq[branch], (4 * quad_of(rr) + hj) * DH + rank * 64, kc * 64, bar, (uint16_t)3);
          } else {
            mbar_expect_tx(bar, Q_HALF);
            tma2d(dst, &maps.x[branch], kc * 64, bidx * SQ, bar);
          }
        }
        gq++;
        if (++slot == nslots) { slot = 0; ph ^= 1; }
      };
      auto load_op = [&]() {
        const bool lo = (isw == share_o);
        if ((go & 7) == 0) seen = 0;
        const uint32_t need = 3u << (go & 6);
        if (lo && (seen & need) != need) {
          uint32_t n = 0;
          while (true) {
            unsigned v;
            asm volatile("ld.acquire.gpu.global.u32 %0, [%1];" : "=r"(v) : "l"(myflag + (go >> 3) * 4) : "memory");
            seen = __ballot_sync(0xffffffff, v == tag);
            if ((seen & need) == need) break;
            if (go < 8 * (NROUND - 1)) __nanosleep(200);
            if (++n > (1u << 22)) asm volatile("trap;");
          }
          asm volatile("fence.proxy.async.global;" ::: "memory");
        }
        mbar_wait(bempty + 8 * slot, ph);
        if (elect_one()) {
          const uint32_t bar = bfull + 8 * slot;
          const uint32_t dst = ring + slot * TILE;
          const CUtensorMap* m = lo ? &maps.oload : &maps.wo[branch];
          const int c0 = lo ? o_block(go >> 3, (go >> 1) & 3) * DH + (go & 1) * 64 : tcol * 128;
          const int c1 = lo ? branch * ROWS + trow * 128 : (8 * quad_of(go >> 3) + (go & 7)) * 64;
          if (!isw && !store_tile) {
            mbar_arrive(bar);
          } else if (isw) {
            mbar_expect_tx(bar, TILE);
            tma2d_mc(dst, m, c0 + (lo ? 0 : rank * 64), c1 + (lo ? rank * 64 : 0), bar, (uint16_t)3);
          } else {
            mbar_expect_tx(bar, TILE);
            tma2d(dst, m, c0, c1, bar);
            tma2d(dst + 8192, m, c0 + (lo ? 0 : 64), c1 + (lo ? 64 : 0), bar);
          }
        }
        go++;
        if (++slot == nslots) { slot = 0; ph ^= 1; }
      };
#pragma unroll 1
      for (int r = -1; r <= NROUND; r++) {
        if (r + 1 < NROUND) {
#pragma unroll 1
          while (gq < 10 * (r + 2)) load_qp();
        }
        if (r == 0) tag = __shfl_sync(0xffffffff, *(volatile unsigned*)&g_epoch + 1, 0);
        if (r > 0) {
#pragma unroll 1
          for (int s = 0; s < 8; s++) {
            if (r == NROUND && (s == 3 || s == 4)) go++;
            else load_op();
          }
        }
      }
    } else {
      auto prefetch_w = [&](int p) {
        if (p + 1 < NROUND && lane < 10) prefetch_l2(maps.pwq[branch] + (size_t)(c64 * 10 + lane) * (HD * 2) + quad_of(p + 1) * 1024, 1024);
        if (p >= 1 && p <= NROUND && lane == 10) prefetch_l2(maps.pwo[branch] + (size_t)(quad_of(p - 1) * 512 + c64 * 8) * (DM * 2), 8 * DM * 2);
      };
      prefetch_w(0);
      const unsigned tag = *(volatile unsigned*)&g_epoch + 1;
#pragma unroll 1
      for (int r = 0; r < NROUND; r++) {
        prefetch_w(r + 1);
        mbar_wait(bar_q_free, r & 1);
        const int prev = r - (hj < O_SINGLE ? 1 : 2);
        if (prev >= 0) {
          const unsigned* u = g_used + (branch * 12 + (bidx * SQ + (lane & 1) * (SQ - 1)) / 128) * NH + 4 * prev + hj;
          uint32_t n = 0;
          while (true) {
            unsigned v;
            asm volatile("ld.acquire.gpu.global.u32 %0, [%1];" : "=r"(v) : "l"(u) : "memory");
            if (__all_sync(0xffffffff, v == tag * 5)) break;
            if (++n > (1u << 22)) asm volatile("trap;");
          }
          asm volatile("fence.proxy.async.global;" ::: "memory");
        }
        mbar_wait(bar_o_staged, r & 1);
        if (lane == 0) {
          const int h = 4 * r + hj;
          const int oc = o_block(r, hj) * DH;
          tma2d_store(&maps.ostore, oc, branch * ROWS + bidx * SQ, sbase + OFF_P);
          tma2d_store(&maps.ostore, oc + 64, branch * ROWS + bidx * SQ, sbase + OFF_P + Q_HALF);
          asm volatile("cp.async.bulk.commit_group;" ::: "memory");
          asm volatile("cp.async.bulk.wait_group.read 0;" ::: "memory");
          mbar_arrive(bar_o_free);
          asm volatile("cp.async.bulk.wait_group 0;" ::: "memory");
          asm volatile("fence.proxy.async.global;" ::: "memory");
          asm volatile("st.release.gpu.global.u32 [%0], %1;" ::"l"(g_flags + (branch * NB + bidx) * NH + h), "r"(tag) : "memory");
        }
        __syncwarp();
      }
      if (lane == 0) {
        const unsigned d = atomicAdd(&g_done, 1u);
        if (d == gridDim.x - 1) {
          g_done = 0;
          g_prog = 0;
          __threadfence();
          atomicAdd(&g_epoch, 1u);
        }
      }
    }
  } else if (warp >= 4) {
    asm volatile("setmaxnreg.inc.sync.aligned.u32 256;");
    const int wq = warp & 3;
    const uint32_t sb16 = (sbase & 0x3FFFF) >> 4;
    uint32_t reladdr;
    asm("mapa.shared::cluster.u32 %0, %1, %2;" : "=r"(reladdr) : "r"(lane < 2 ? bar_w_empty : bar_x_empty), "r"(lane < 2 ? lane : rank));
    const uint32_t relend = reladdr + 8 * (lane < 2 ? W_SLOTS : X_SLOTS);
    float out0[64], out1[64], qa0[48], qa1[48];
#pragma unroll
    for (int i = 0; i < 64; i++) { out0[i] = 0.f; out1[i] = 0.f; }
#pragma unroll
    for (int i = 0; i < 48; i++) { qa0[i] = 0.f; qa1[i] = 0.f; }
    int ws = 0; uint32_t wp = 0;
    int xs = 0; uint32_t xp = 0;
    uint32_t pend = 0;

    auto w_release = [&](uint32_t on) {
      arrive_cluster_if(reladdr, on && lane < 3);
      if (on) reladdr += 8;
      if (reladdr == relend) reladdr -= 8 * (lane < 2 ? W_SLOTS : X_SLOTS);
    };
    auto acquire = [&]() {
      if (!mbar_test2(bar_w_full + 8 * ws, wp, bar_x_full + 8 * xs, xp)) {
        wg_wait<0>();
        w_release(pend);
        pend = 0;
        mbar_wait2(bar_w_full + 8 * ws, wp, bar_x_full + 8 * xs, xp);
      }
    };
    auto advance = [&]() {
      if (++ws == W_SLOTS) { ws = 0; wp ^= 1; }
      if (++xs == X_SLOTS) { xs = 0; xp ^= 1; }
      pend = 1;
    };
    auto q_store = [&]() {
      const uint32_t tst = sbase + OFF_Q + ((lane >> 4) * 8 + (lane & 7)) * 128 + (((2 * wq + ((lane >> 3) & 1)) ^ (lane & 7)) << 4);
#pragma unroll
      for (int j = 0; j < 6; j++) {
        stsm4_t(tst + j * 2048, pack_bf16(qa0[8 * j + 0], qa0[8 * j + 1]), pack_bf16(qa0[8 * j + 2], qa0[8 * j + 3]),
                pack_bf16(qa0[8 * j + 4], qa0[8 * j + 5]), pack_bf16(qa0[8 * j + 6], qa0[8 * j + 7]));
        stsm4_t(tst + Q_HALF + j * 2048, pack_bf16(qa1[8 * j + 0], qa1[8 * j + 1]), pack_bf16(qa1[8 * j + 2], qa1[8 * j + 3]),
                pack_bf16(qa1[8 * j + 4], qa1[8 * j + 5]), pack_bf16(qa1[8 * j + 6], qa1[8 * j + 7]));
      }
      fence_async_smem();
      __syncwarp();
      arrive_if(bar_q_ready, lane == 0);
    };

#pragma unroll
    for (int kc = 0; kc < 10; kc++) {
      const bool bw = kc >= W_SLOTS && kc < W_SLOTS + KV_SLOTS, bx = kc >= X_SLOTS && kc < X_SLOTS + 4;
      const uint32_t alo = sb16 + LBO1K + (bw ? (OFF_KV >> 4) + (kc - W_SLOTS) * 1024 : (OFF_W >> 4) + ws * 1024);
      const uint32_t blo = sb16 + LBO1 + (bx ? (OFF_Q >> 4) + (kc - X_SLOTS) * 768 : (OFF_X >> 4) + xs * 1024);
      mbar_wait2(bw ? bar_kv_full + 8 * (kc - W_SLOTS) : bar_w_full + 8 * ws, bw ? 0 : wp,
                 bx ? bar_x0 + 8 * (kc - X_SLOTS) : bar_x_full + 8 * xs, bx ? 0 : xp);
      wg_fence();
#pragma unroll
      for (int k = 0; k < 4; k++) {
        mma_t96(qa0, alo + 128 * k, blo + 2 * k);
        mma_t96(qa1, alo + 512 + 128 * k, blo + 2 * k);
      }
      wg_commit();
      if (!bw && ++ws == W_SLOTS) { ws = 0; wp ^= 1; }
      if (!bx && ++xs == X_SLOTS) { xs = 0; xp ^= 1; }
      if (kc == 9) wg_wait<0>(); else wg_wait<1>();
#pragma unroll
      for (int d = (kc > 0 ? kc - 1 : 1); d <= (kc == 9 ? 9 : kc - 1); d++) {
        const bool dw = d >= W_SLOTS && d < W_SLOTS + KV_SLOTS, dx = d >= X_SLOTS && d < X_SLOTS + 4;
        if (dw) arrive_if(bar_kv_empty + 8 * (d - W_SLOTS), lane == 0);
        w_release(lane < 2 ? !dw : !dx);
      }
    }
    pin(qa0);
    pin(qa1);
    asm volatile("bar.sync 2, 128;" ::: "memory");
    q_store();
#pragma unroll 1
    for (int r = 0; r < NROUND; r++) {
      bool owe_q = false;
      if (r + 1 < NROUND) {
#pragma unroll 1
        for (int kc = 0; kc < 10; kc++) {
          const uint32_t alo = sb16 + (OFF_W >> 4) + LBO1K + ws * 1024;
          const uint32_t blo = sb16 + (OFF_X >> 4) + LBO1 + xs * 1024;
          acquire();
#pragma unroll
          for (int k = 0; k < 4; k++) {
            wg_fence();
            if (k == 0) {
              mma_t96p(qa0, alo, blo, kc);
              mma_t96p(qa1, alo + 512, blo, kc);
            } else {
              mma_t96(qa0, alo + 128 * k, blo + 2 * k);
              mma_t96(qa1, alo + 512 + 128 * k, blo + 2 * k);
            }
            wg_commit();
            wg_wait<PDEPTH>();
            if (k == PDEPTH - 1) w_release(pend);
          }
          advance();
        }
        owe_q = true;
      }
      if (r > 0) {
#pragma unroll 1
        for (int s = 0; s < 8; s++) {
          const uint32_t xd = sb16 + (OFF_X >> 4) + xs * 1024, wd = sb16 + (OFF_W >> 4) + ws * 1024;
          const uint32_t alo = (share_o ? wd : xd) + LBO1;
          const uint32_t blo = (share_o ? xd : wd) + LBO8K;
          acquire();
          if ((s & 1) && threadIdx.x == 128 && store_tile)
            asm volatile("red.relaxed.gpu.global.add.u32 [%0], 1;" ::"l"(g_used + (branch * 12 + trow) * NH + 4 * (r - 1) + (s >> 1)) : "memory");
#pragma unroll
          for (int k = 0; k < 4; k++) {
            wg_fence();
            if (store_tile) {
              mma_op(out0, alo + 2 * k, blo + 128 * k);
              mma_op(out1, alo + 512 + 2 * k, blo + 128 * k);
              wg_commit();
            } else {
              wg_commit();
            }
            wg_wait<PDEPTH>();
            if (k == PDEPTH - 1) w_release(pend);
          }
          advance();
          pin(qa0);
          pin(qa1);
          if (owe_q && mbar_test(bar_q_free, r & 1)) {
            q_store();
            owe_q = false;
          }
        }
      }
      if (owe_q) {
        wg_wait<0>();
        pin(qa0);
        pin(qa1);
        w_release(pend);
        pend = 0;
        mbar_wait(bar_q_free, r & 1);
        q_store();
      }
    }
    {
#pragma unroll 1
      for (int s = 0; s < 6; s++) {
        const bool ext = (s == 3 || s == 4);
        const uint32_t xd = sb16 + (OFF_X >> 4) + xs * 1024, wd = sb16 + (OFF_W >> 4) + ws * 1024;
        uint32_t alo = (share_o ? wd : xd) + LBO1;
        uint32_t blo = (share_o ? xd : wd) + LBO8K;
        if (ext) {
          alo = sb16 + (OFF_KV >> 4) + LBO1 + (s == 3 ? tail_slot(2) : tail_slot(3)) * 1024;
          blo = sb16 + (OFF_KV >> 4) + LBO8K + (s == 3 ? tail_slot(0) : tail_slot(1)) * 1024;
          if (!mbar_test2(bar_x0 + 8 * (s - 3), 1, bar_x0 + 8 * (s - 1), 1)) {
            wg_wait<0>();
            w_release(pend);
            pend = 0;
            mbar_wait2(bar_x0 + 8 * (s - 3), 1, bar_x0 + 8 * (s - 1), 1);
          }
        } else {
          acquire();
        }
        wg_fence();
#pragma unroll
        for (int k = 0; k < 4; k++) mma_op(out0, alo + 2 * k, blo + 128 * k);
        wg_commit();
        wg_wait<1>();
        w_release(pend);
        wg_fence();
#pragma unroll
        for (int k = 0; k < 4; k++) mma_op(out1, alo + 512 + 2 * k, blo + 128 * k);
        wg_commit();
        if (!ext) advance();
        pend = (s < 3) && (s < 6 - (lane < 2 ? W_SLOTS : X_SLOTS));
      }
      {
        const uint32_t xd = sb16 + (OFF_X >> 4) + xs * 1024, wd = sb16 + (OFF_W >> 4) + ws * 1024;
        const uint32_t a6 = (share_o ? wd : xd) + LBO1, b6 = (share_o ? xd : wd) + LBO8K;
        mbar_wait2(bar_w_full + 8 * ws, wp, bar_x_full + 8 * xs, xp);
        advance();
        const uint32_t xe = sb16 + (OFF_X >> 4) + xs * 1024, we = sb16 + (OFF_W >> 4) + ws * 1024;
        const uint32_t a7 = (share_o ? we : xe) + LBO1, b7 = (share_o ? xe : we) + LBO8K;
        wg_fence();
#pragma unroll
        for (int k = 0; k < 4; k++) mma_op(out0, a6 + 2 * k, b6 + 128 * k);
        wg_commit();
        mbar_wait2(bar_w_full + 8 * ws, wp, bar_x_full + 8 * xs, xp);
        wg_fence();
#pragma unroll
        for (int k = 0; k < 4; k++) mma_op(out0, a7 + 2 * k, b7 + 128 * k);
        wg_commit();
        asm volatile("bar.sync 2, 128;" ::: "memory");
        wg_fence();
#pragma unroll
        for (int k = 0; k < 4; k++) mma_op(out1, a6 + 512 + 2 * k, b6 + 128 * k);
#pragma unroll
        for (int k = 0; k < 4; k++) mma_op(out1, a7 + 512 + 2 * k, b7 + 128 * k);
        wg_commit();
      }
      const int t = lane & 7, mi = lane >> 3;
      auto out_store = [&](float (&acc)[64], int half) {
        const uint32_t stage = sbase + OFF_KV + tail_slot(half) * TILE + wq * 4096;
#pragma unroll
        for (int rh = 0; rh < 2; rh++) {
#pragma unroll
          for (int jj = 0; jj < 4; jj++) {
            const int o = 16 * jj + 2 * rh;
            stsm4(stage + (rh * 8 + t) * 256 + (((4 * jj + mi) ^ t) << 4), pack_bf16(acc[o + 0], acc[o + 1]), pack_bf16(acc[o + 4], acc[o + 5]),
                  pack_bf16(acc[o + 8], acc[o + 9]), pack_bf16(acc[o + 12], acc[o + 13]));
          }
        }
        __syncwarp();
        uint8_t* g = maps.pout + ((size_t)(trow * 128 + half * 64 + wq * 16 + (lane >> 4)) * (2 * DM) + branch * DM + tcol * 128) * 2 + (lane & 15) * 16;
        uint4 v[8];
#pragma unroll
        for (int i = 0; i < 8; i++) {
          const int row = 2 * i + (lane >> 4);
          asm volatile("ld.shared.v4.u32 {%0, %1, %2, %3}, [%4];" : "=r"(v[i].x), "=r"(v[i].y), "=r"(v[i].z), "=r"(v[i].w)
                       : "r"(stage + row * 256 + (((lane & 15) ^ (row & 7)) << 4)) : "memory");
        }
        if (store_tile) {
#pragma unroll
          for (int i = 0; i < 8; i++) *reinterpret_cast<uint4*>(g + (size_t)i * (2 * 2 * DM * 2)) = v[i];
        }
      };
      wg_wait<1>();
      pin(out0);
      out_store(out0, 0);
      wg_wait<0>();
      pin(out1);
      out_store(out1, 1);
    }
    wg_wait<0>();
  } else {
    asm volatile("setmaxnreg.inc.sync.aligned.u32 224;");
    const uint32_t sb16 = (sbase & 0x3FFFF) >> 4;
    const bool bit2 = lane & 4, bit3 = lane & 8, bit4 = lane & 16;
    const uint32_t tst = sbase + OFF_P + ((lane >> 4) * 8 + (lane & 7)) * 128 + (((2 * warp + ((lane >> 3) & 1)) ^ (lane & 7)) << 4);
    const float cscale = 0.08838834764831845f * 1.4426950408889634f;
    const float2* mc2 = reinterpret_cast<const float2*>(smem_raw + OFF_MC) + (lane & 3);
    const float2* fac2 = reinterpret_cast<const float2*>(smem_raw + OFF_FAC) + (lane & 3);
    const uint32_t own = sbase + OFF_LP + warp * 384 + ((lane >> 3) * 8 + (lane & 3) * 2 + ((lane >> 2) & 1)) * 4;
    const uint32_t lane0 = (lane == 0);

    float ot0[48], ot1[48], s[48] = {}, l[24], nm[24];
#pragma unroll
    for (int i = 0; i < 48; i++) { ot0[i] = 0.f; ot1[i] = 0.f; }
    int ks = 0, kr = 0; uint32_t kp = 1;

    auto col_reduce = [&](auto get, auto op) {
      float v[12], u[6], w[3];
#pragma unroll
      for (int i = 0; i < 12; i++) {
        const float x = get(2 * i), y = get(2 * i + 1);
        v[i] = op(bit2 ? y : x, __shfl_xor_sync(0xffffffff, bit2 ? x : y, 4));
      }
#pragma unroll
      for (int i = 0; i < 6; i++)
        u[i] = op(bit3 ? v[2 * i + 1] : v[2 * i], __shfl_xor_sync(0xffffffff, bit3 ? v[2 * i] : v[2 * i + 1], 8));
#pragma unroll
      for (int i = 0; i < 3; i++)
        w[i] = op(bit4 ? u[2 * i + 1] : u[2 * i], __shfl_xor_sync(0xffffffff, bit4 ? u[2 * i] : u[2 * i + 1], 16));
#pragma unroll
      for (int i = 0; i < 3; i++) sts32(own + i * 128, w[i]);
      bar_sync_wg();
    };
    auto col_max = [&]() -> float {
      col_reduce([&](int c) { return fmaxf(s[4 * (c >> 1) + (c & 1)], s[4 * (c >> 1) + (c & 1) + 2]); },
                 [](float a, float b) { return fmaxf(a, b); });
      const float* pm = reinterpret_cast<const float*>(smem_raw + OFF_LP) + min((int)threadIdx.x, SQ - 1);
      return fmaxf(fmaxf(pm[0], pm[96]), fmaxf(pm[192], pm[288]));
    };
    auto load_max = [&]() {
#pragma unroll
      for (int blk = 0; blk < 12; blk++) {
        const float2 m = mc2[blk * 4];
        nm[2 * blk] = m.x; nm[2 * blk + 1] = m.y;
      }
    };
    auto qk_issue = [&]() {
      const uint32_t alo = sb16 + (OFF_KV >> 4) + LBO1 + ks * 1024;
      const uint32_t blo = sb16 + (OFF_Q >> 4) + LBO1;
      wg_fence();
      mma_qk0(s, alo, blo);
#pragma unroll
      for (int k = 1; k < 8; k++) mma_qk(s, alo + (k >> 2) * 512 + 2 * (k & 3), blo + (k >> 2) * 768 + 2 * (k & 3));
      wg_commit();
      if (++ks == KV_SLOTS) { ks = 0; kp ^= 1; }
    };
    auto kv_release = [&]() {
      arrive_if(bar_kv_empty + 8 * kr, lane0);
      if (++kr == KV_SLOTS) kr = 0;
    };
    auto pv_issue = [&](int pb, uint32_t acc) {
      const uint32_t alo = sb16 + (OFF_KV >> 4) + LBO1K + ks * 1024;
      const uint32_t blo = sb16 + (OFF_P >> 4) + LBO1 + pb * 768;
      fence_async_smem();
      mbar_wait(bar_kv_full + 8 * ks, kp);
      bar_sync_wg();
      wg_fence();
      mma_t96p(ot0, alo, blo, acc);
      mma_t96p(ot1, alo + 512, blo, acc);
#pragma unroll
      for (int k = 1; k < 4; k++) {
        mma_t96(ot0, alo + 128 * k, blo + 2 * k);
        mma_t96(ot1, alo + 512 + 128 * k, blo + 2 * k);
      }
      wg_commit();
      if (++ks == KV_SLOTS) { ks = 0; kp ^= 1; }
    };
    uint32_t nrdy = 0;
    auto shift_block = [&]() {
#pragma unroll
      for (int i = 0; i < 48; i++) s[i] = fmaf(s[i], cscale, nm[(i >> 2) * 2 + (i & 1)]);
    };
    auto exp_block = [&](uint32_t dst) {
#pragma unroll
      for (int q = 0; q < 6; q++) {
        if (q == VREL_Q) { wg_wait<0>(); kv_release(); nrdy = mbar_test(bar_kv_full + 8 * ks, kp); }
        float e[8];
#pragma unroll
        for (int i = 0; i < 8; i++) e[i] = ex2(s[8 * q + i]);
#pragma unroll
        for (int c = 0; c < 4; c++) {
          l[4 * q + c] += e[(c >> 1) * 4 + (c & 1)] + e[(c >> 1) * 4 + (c & 1) + 2];
        }
        stsm4_t(dst + q * 2048, pack_bf16(e[0], e[1]), pack_bf16(e[2], e[3]), pack_bf16(e[4], e[5]), pack_bf16(e[6], e[7]));
      }
    };

    mbar_wait(bar_q_ready, 0);
    mbar_wait(bar_kv_full, 1);
    qk_issue();
#pragma unroll 1
    for (int r = 0; r < NROUND; r++) {
      wg_wait<0>();
      pin(s);
      kv_release();
      {
        const float m = col_max();
        if (threadIdx.x < SQ) sts32(sbase + OFF_MC + threadIdx.x * 4, -m * cscale);
        bar_sync_wg();
        load_max();
        shift_block();
        uint32_t pk[24];
#pragma unroll
        for (int i = 0; i < 48; i++) s[i] = ex2(s[i]);
#pragma unroll
        for (int i = 0; i < 24; i++) {
          l[i] = s[4 * (i >> 1) + (i & 1)] + s[4 * (i >> 1) + (i & 1) + 2];
          pk[i] = pack_bf16(s[2 * i], s[2 * i + 1]);
          asm volatile("" : "+r"(pk[i]));
        }
        if (r > 0) mbar_wait(bar_o_free, (r - 1) & 1);
#pragma unroll
        for (int q = 0; q < 6; q++) stsm4_t(tst + q * 2048, pk[4 * q], pk[4 * q + 1], pk[4 * q + 2], pk[4 * q + 3]);
        mbar_wait(bar_kv_full + 8 * ks, kp);
      }
#pragma unroll 1
      for (int j = 1; j < 8; j++) {
        const uint32_t pdst = tst + (j & 1) * Q_HALF;
        qk_issue();
        pv_issue((j - 1) & 1, j - 1);
        wg_wait<1>();
        pin(s);
        kv_release();
        arrive_if(bar_q_free, lane0 && j == 7);
        shift_block();
        int tm[4] = {0, 0, 0, 0};
#pragma unroll
        for (int i = 0; i < 24; i++) tm[i & 3] = __vimax3_s32(tm[i & 3], __float_as_int(s[2 * i]), __float_as_int(s[2 * i + 1]));
        if (__any_sync(0xffffffff, bar_or_wg(max(__vimax3_s32(tm[0], tm[1], tm[2]), tm[3]) > __float_as_int(T_LIMIT)))) {
          wg_wait<0>();
          pin(ot0);
          pin(ot1);
          const float d = -fmaxf(col_max(), 0.f);
          if (threadIdx.x < SQ) sts32(sbase + OFF_FAC + threadIdx.x * 4, d);
          bar_sync_wg();
#pragma unroll
          for (int blk = 0; blk < 12; blk++) {
            const float2 nd = fac2[blk * 4];
            const float fx = ex2(nd.x), fy = ex2(nd.y);
            nm[2 * blk] += nd.x; nm[2 * blk + 1] += nd.y;
            s[4 * blk] += nd.x; s[4 * blk + 1] += nd.y; s[4 * blk + 2] += nd.x; s[4 * blk + 3] += nd.y;
            ot0[4 * blk] *= fx; ot0[4 * blk + 1] *= fy; ot0[4 * blk + 2] *= fx; ot0[4 * blk + 3] *= fy;
            ot1[4 * blk] *= fx; ot1[4 * blk + 1] *= fy; ot1[4 * blk + 2] *= fx; ot1[4 * blk + 3] *= fy;
            l[2 * blk] *= fx; l[2 * blk + 1] *= fy;
          }
        }
        exp_block(pdst);
        if (!__all_sync(0xffffffff, nrdy)) mbar_wait(bar_kv_full + 8 * ks, kp);
      }
      pv_issue(1, 1);
      col_reduce([&](int c) { return l[c]; }, [](float a, float b) { return a + b; });
      if (threadIdx.x < SQ) {
        const float* lp = reinterpret_cast<const float*>(smem_raw + OFF_LP) + threadIdx.x;
        sts32(sbase + OFF_FAC + threadIdx.x * 4, 1.0f / ((lp[0] + lp[96]) + (lp[192] + lp[288])));
      }
      bar_sync_wg();
#pragma unroll
      for (int blk = 0; blk < 12; blk++) {
        const float2 f = fac2[blk * 4];
        l[2 * blk] = f.x; l[2 * blk + 1] = f.y;
      }
      if (r + 1 < NROUND) {
        mbar_wait2(bar_q_ready, (r + 1) & 1, bar_kv_full + 8 * ks, kp);
        qk_issue();
        wg_wait<1>();
      } else {
        wg_wait<0>();
#pragma unroll
        for (int i = 0; i < 48; i++) s[i] = 0.f;
      }
      pin(ot0);
      pin(ot1);
      kv_release();
      bar_sync_wg();
#pragma unroll
      for (int jj = 0; jj < 6; jj++) {
        const float fx = l[4 * jj], fy = l[4 * jj + 1], gx = l[4 * jj + 2], gy = l[4 * jj + 3];
        stsm4_t(tst + jj * 2048, pack_bf16(ot0[8 * jj] * fx, ot0[8 * jj + 1] * fy), pack_bf16(ot0[8 * jj + 2] * fx, ot0[8 * jj + 3] * fy),
                pack_bf16(ot0[8 * jj + 4] * gx, ot0[8 * jj + 5] * gy), pack_bf16(ot0[8 * jj + 6] * gx, ot0[8 * jj + 7] * gy));
        stsm4_t(tst + Q_HALF + jj * 2048, pack_bf16(ot1[8 * jj] * fx, ot1[8 * jj + 1] * fy), pack_bf16(ot1[8 * jj + 2] * fx, ot1[8 * jj + 3] * fy),
                pack_bf16(ot1[8 * jj + 4] * gx, ot1[8 * jj + 5] * gy), pack_bf16(ot1[8 * jj + 6] * gx, ot1[8 * jj + 7] * gy));
      }
      fence_async_smem();
      __syncwarp();
      arrive_if(bar_o_staged, lane0);
    }
    wg_wait<0>();
  }
}

typedef CUresult (*EncodeFn)(CUtensorMap*, CUtensorMapDataType, cuuint32_t, void*, const cuuint64_t*, const cuuint64_t*,
                             const cuuint32_t*, const cuuint32_t*, CUtensorMapInterleave, CUtensorMapSwizzle,
                             CUtensorMapL2promotion, CUtensorMapFloatOOBfill);

void make2d(EncodeFn enc, CUtensorMap* m, const void* ptr, uint64_t cols, uint64_t rows, uint32_t boxc, uint32_t boxr,
            CUtensorMapL2promotion promo) {
  cuuint64_t gd[2] = {cols, rows};
  cuuint64_t gs[1] = {cols * 2};
  cuuint32_t bx[2] = {boxc, boxr};
  cuuint32_t es[2] = {1, 1};
  enc(m, CU_TENSOR_MAP_DATA_TYPE_BFLOAT16, 2, const_cast<void*>(ptr), gd, gs, bx, es, CU_TENSOR_MAP_INTERLEAVE_NONE,
      CU_TENSOR_MAP_SWIZZLE_128B, promo, CU_TENSOR_MAP_FLOAT_OOB_FILL_NONE);
}

}

extern "C" void kernel_launch(void* const* d_in, const int* in_sizes, int n_in, void* d_out, int out_size) {
  (void)in_sizes; (void)n_in; (void)out_size;
  void* fn = nullptr;
  cudaDriverEntryPointQueryResult qr;
  cudaGetDriverEntryPoint("cuTensorMapEncodeTiled", &fn, cudaEnableDefault, &qr);
  EncodeFn enc = (EncodeFn)fn;
  void* oscratch = nullptr;
  cudaGetSymbolAddress(&oscratch, g_O);
  Maps maps;
  for (int br = 0; br < 2; br++) {
    const void* x = d_in[5 * br + 0];
    const void* k = d_in[5 * br + 1];
    const void* v = d_in[5 * br + 2];
    const void* wq = d_in[5 * br + 3];
    const void* wo = d_in[5 * br + 4];
    for (int kv = 0; kv < 2; kv++) {
      cuuint64_t gd[3] = {64, (cuuint64_t)NB * NH * SK, 2};
      cuuint64_t gs[2] = {256, 128};
      cuuint32_t bx[3] = {64, 64, 2};
      cuuint32_t es[3] = {1, 1, 1};
      enc(kv ? &maps.v[br] : &maps.k[br], CU_TENSOR_MAP_DATA_TYPE_BFLOAT16, 3, const_cast<void*>(kv ? v : k), gd, gs, bx, es,
          CU_TENSOR_MAP_INTERLEAVE_NONE, CU_TENSOR_MAP_SWIZZLE_128B, CU_TENSOR_MAP_L2_PROMOTION_L2_128B,
          CU_TENSOR_MAP_FLOAT_OOB_FILL_NONE);
    }
    maps.pwq[br] = (const uint8_t*)wq;
    maps.pwo[br] = (const uint8_t*)wo;
    make2d(enc, &maps.x[br], x, DM, ROWS, 64, SQ, CU_TENSOR_MAP_L2_PROMOTION_L2_128B);
    make2d(enc, &maps.wq[br], wq, HD, DM, 64, 64, CU_TENSOR_MAP_L2_PROMOTION_L2_128B);
    make2d(enc, &maps.wo[br], wo, DM, HD, 64, 64, CU_TENSOR_MAP_L2_PROMOTION_L2_128B);
  }
  make2d(enc, &maps.oload, oscratch, O_BLOCKS * DH, 2 * ROWS, 64, 64, CU_TENSOR_MAP_L2_PROMOTION_L2_128B);
  make2d(enc, &maps.ostore, oscratch, O_BLOCKS * DH, 2 * ROWS, 64, SQ, CU_TENSOR_MAP_L2_PROMOTION_NONE);
  maps.pout = (uint8_t*)d_out;
  cudaFuncSetAttribute(fused_attn_kernel, cudaFuncAttributeMaxDynamicSharedMemorySize, SMEM_BYTES);
  fused_attn_kernel<<<128, 384, SMEM_BYTES>>>(maps);
}
```
